```python
import torch

def _softmax(x, axis=-1):
    return torch.softmax(x, dim=axis)
def _gelu(x):
    return torch.nn.functional.gelu(x, approximate="tanh")
def _silu(x):
    return torch.nn.functional.silu(x)
def _sigmoid(x):
    return torch.sigmoid(x)
def _layernorm(x, axis=-1, eps=1e-5):
    m = x.mean(dim=axis, keepdim=True)
    v = x.var(dim=axis, keepdim=True, unbiased=False)
    return (x - m) / torch.sqrt(v + eps)
def _scatter_add(tgt, idx, src, axis=0):
    return tgt.clone().index_add_(axis, idx, src)
def _segment_sum(src, seg, n):
    out = torch.zeros((n,) + src.shape[1:], dtype=src.dtype)
    return out.index_add_(0, seg, src)
def _pad(x, pw):
    flat = tuple(v for pair in reversed(pw) for v in pair)
    return torch.nn.functional.pad(x, flat)

kernel_name = 'parallel_sum__grouped_kv_mqa__dense_activation_relu__prompt'

def setup_inputs():

    _w = (lambda a: (lambda t: t.to(torch.bfloat16) if t.is_floating_point() else t)(torch.as_tensor(a)))
    def _A_setup():
        B, S, D, H = 1, 2048, 512, 32
        Dh = D // H
        return {
            "x": _w((lambda *s: torch.randn(*s, dtype=torch.bfloat16) * 0.05)(B, S, D)),
            "wq": _w((lambda *s: torch.randn(*s, dtype=torch.bfloat16) * 0.2)(D, H * Dh)),
            "wk": _w((lambda *s: torch.randn(*s, dtype=torch.bfloat16) * 0.2)(D, Dh)),
            "wv": _w((lambda *s: torch.randn(*s, dtype=torch.bfloat16) * 0.1)(D, Dh)),
            "wo": _w((lambda *s: torch.randn(*s, dtype=torch.bfloat16) * 0.1)(H * Dh, D)),
        }
    _A_in = _A_setup()

    def _B_setup():
        B, S, D, Dff = 1, 2048, 512, 1792
        return {
            "x": _w((lambda *s: torch.randn(*s, dtype=torch.bfloat16) * 0.05)(B, S, D)),
            "w1": _w((lambda *s: torch.randn(*s, dtype=torch.bfloat16) * 0.1)(D, Dff)),
            "w2": _w((lambda *s: torch.randn(*s, dtype=torch.bfloat16) * 0.1)(Dff, D)),
        }
    _B_in = _B_setup()

    return {
        "A_x": _A_in["x"],
        "A_wq": _A_in["wq"],
        "A_wk": _A_in["wk"],
        "A_wv": _A_in["wv"],
        "A_wo": _A_in["wo"],
        "B_x": _B_in["x"],
        "B_w1": _B_in["w1"],
        "B_w2": _B_in["w2"],
    }

def reference(A_x, A_wq, A_wk, A_wv, A_wo, B_x, B_w1, B_w2):
    def _A_ref(x, wq, wk, wv, wo):
        B, S, D = x.shape
        H = 32
        Dh = D // H
        q = (lambda x, *d: x.permute(*d))((x @ wq).reshape(B, S, H, Dh), 0, 2, 1, 3)
        k = x @ wk
        v = x @ wv
        scores = torch.einsum("bhqd,bkd->bhqk", q, k) * (Dh ** -0.5)
        p = _softmax(scores, axis=-1)
        o = torch.einsum("bhqk,bkd->bhqd", p, v)
        return (lambda x, *d: x.permute(*d))(o, 0, 2, 1, 3).reshape(B, S, H * Dh) @ wo

    def _B_ref(x, w1, w2):
        h = torch.einsum("bsd,df->bsf", x, w1)
        zero = torch.zeros_like(h)
        h = torch.maximum(h, zero)
        return torch.einsum("bsf,fd->bsd", h, w2)

    x = A_x
    xn = _layernorm(x, axis=-1)
    return x + _A_ref(xn, A_wq, A_wk, A_wv, A_wo) + _B_ref(xn, B_w1, B_w2)
```

```cpp
#include <cuda_runtime.h>
#include <cuda_bf16.h>
#include <cuda.h>
#include <stdint.h>

#define PM_POLY 0x05550505u
#define NS_KV 200
#define NS_GP 100
#define NS_GC 40
#define R_ATT 184
#define R_GEM 112
#define R_PRO 32

namespace {

constexpr int D_MODEL = 512, D_FF = 1792;

constexpr int OFF_XN = 0;
constexpr int G_SLOT = 24576, NG = 4;
constexpr int OFF_G = 65536;
constexpr int KV_SLOT = 10240, NKV = 4;
constexpr int OFF_KV = OFF_G + NG * G_SLOT;
constexpr int OFF_Q2 = OFF_KV + NKV * KV_SLOT;
constexpr int OFF_OS = OFF_Q2 + 8192;
constexpr int OFF_AUG = OFF_OS + 8192;
constexpr int OFF_QM = OFF_AUG + 2048;
constexpr int OFF_BAR = OFF_QM + 2048;
constexpr int SMEM_BYTES = OFF_BAR + 512 + 1024;
constexpr int OFF_WKV = OFF_G, OFF_WQ1 = OFF_G + 32768;
constexpr int B_ST = 0, B_WKV = 8, B_WQ1 = 16, B_PRO = 32, B_Q2 = 40, B_HR = 48  , B_KVF = 72  , B_KVE = 104  , B_GF = 136  ,
              B_GE = 168  , B_OR = 208  , B_OE = 232, B_NEAR = 240;
constexpr int B_EPOCH = 200, B_ABORT = 204, B_STAT = 224  , B_KEST = 248  ;

static_assert(OFF_BAR % 256 == 0 && SMEM_BYTES <= 232448, "shared memory map");
static_assert((PM_POLY & ~0x55555555u) == 0 && ((PM_POLY & 0x11111111u) << 2) == (PM_POLY & 0x44444444u), "even keys only, both row halves together");
static_assert(2 * R_ATT + R_GEM + R_PRO <= 512, "register budget");

__device__ __align__(1024) uint8_t g_kv[16 * KV_SLOT];
__device__ __align__(1024) uint8_t g_h[32 * 56 * 4096];
__device__ __align__(1024) uint8_t g_o[32 * 16 * 4096];
__device__ __align__(1024) uint8_t g_stats[128 * 32];
__device__ unsigned g_sync[113 * 32];
constexpr int SY_EPOCH = 0, SY_KV = 32, SY_H = 17 * 32, SY_O = 49 * 32;

struct Maps { CUtensorMap wq64, w1a, w1b, w2, wo; };

__device__ __forceinline__ void wg_fence() { asm volatile("wgmma.fence.sync.aligned;" ::: "memory"); }
__device__ __forceinline__ void wg_commit() { asm volatile("wgmma.commit_group.sync.aligned;" ::: "memory"); }
template <int N> __device__ __forceinline__ void wg_wait() { asm volatile("wgmma.wait_group.sync.aligned %0;" ::"n"(N) : "memory"); }
template <int N> __device__ __forceinline__ void pin(float (&r)[N]) {
#pragma unroll
    for (int i = 0; i < N; i++) asm volatile("" : "+f"(r[i])::"memory");
}
template <int N> __device__ __forceinline__ void pin(uint32_t (&r)[N]) {
#pragma unroll
    for (int i = 0; i < N; i++) asm volatile("" : "+r"(r[i])::"memory");
}
__device__ __forceinline__ void pin4(uint32_t* r) { asm volatile("" : "+r"(r[0]), "+r"(r[1]), "+r"(r[2]), "+r"(r[3])::"memory"); }
__device__ __forceinline__ void mbar_init(uint32_t a, int c) { asm volatile("mbarrier.init.shared::cta.b64 [%0], %1;" ::"r"(a), "r"(c) : "memory"); }
__device__ __forceinline__ void mbar_expect(uint32_t a, uint32_t b) { asm volatile("mbarrier.arrive.expect_tx.shared::cta.b64 _, [%0], %1;" ::"r"(a), "r"(b) : "memory"); }
__device__ __forceinline__ void mbar_arrive(uint32_t a) { asm volatile("mbarrier.arrive.shared::cta.b64 _, [%0];" ::"r"(a) : "memory"); }
__device__ __forceinline__ void mbar_arrive_n(uint32_t a, uint32_t n) { asm volatile("mbarrier.arrive.shared::cta.b64 _, [%0], %1;" ::"r"(a), "r"(n) : "memory"); }
__device__ __forceinline__ uint32_t mbar_try(uint32_t a, uint32_t ph) {
    uint32_t r;
    asm volatile("{\n.reg .pred p;\nmbarrier.try_wait.parity.shared::cta.b64 p, [%1], %2;\nselp.u32 %0, 1, 0, p;\n}" : "=r"(r) : "r"(a), "r"(ph) : "memory");
    return r;
}
__device__ __forceinline__ uint32_t mbar_test(uint32_t a, uint32_t ph) {
    uint32_t r;
    asm volatile("{\n.reg .pred p;\nmbarrier.test_wait.parity.shared::cta.b64 p, [%1], %2;\nselp.u32 %0, 1, 0, p;\n}" : "=r"(r) : "r"(a), "r"(ph) : "memory");
    return r;
}
__device__ __forceinline__ bool give_up(uint32_t abort_addr, int n, int limit) {
    uint32_t v;
    asm volatile("ld.volatile.shared.u32 %0, [%1];" : "=r"(v) : "r"(abort_addr) : "memory");
    if (n < limit && v == 0) return false;
    asm volatile("st.volatile.shared.u32 [%0], 1;" ::"r"(abort_addr) : "memory");
    return true;
}
template <int NS = 0>
__device__ __forceinline__ void mbar_wait(uint32_t a, uint32_t ph) {
    if (mbar_try(a, ph)) return;
#pragma unroll 1
    for (int n = 0;; n++) {
        if (NS) __nanosleep(NS);
        if (mbar_try(a, ph)) break;
        if ((n & 7) == 7 && give_up((a & ~255u) + B_ABORT, n, 1 << 23)) break;
    }
}
__device__ __forceinline__ unsigned ld_relaxed(const unsigned* p) {
    unsigned v;
    asm volatile("ld.relaxed.gpu.global.u32 %0, [%1];" : "=r"(v) : "l"(p) : "memory");
    return v;
}
__device__ __forceinline__ void flag_acquired() {
    asm volatile("fence.proxy.async.global;" ::: "memory");
}
__device__ __forceinline__ void flag_wait(const unsigned* p, unsigned target, unsigned sleep_ns, uint32_t bar) {
#pragma unroll 1
    for (int n = 0;; n++) {
        if ((int)(ld_relaxed(p) - target) >= 0) break;
        if ((n & 15) == 15 && give_up(bar + B_ABORT, n, 1 << 22)) break;
        __nanosleep(sleep_ns);
    }
    flag_acquired();
}
__device__ __forceinline__ void flag_wait_fast(const unsigned* p, unsigned target, uint32_t bar) {
    unsigned v0 = ld_relaxed(p);
    __nanosleep(80);
    unsigned v1 = ld_relaxed(p);
    __nanosleep(80);
    unsigned v2 = ld_relaxed(p);
    __nanosleep(80);
#pragma unroll 1
    for (int n = 0;; n++) {
        const unsigned v3 = ld_relaxed(p);
        if ((int)(v0 - target) >= 0) break;
        v0 = ld_relaxed(p);
        if ((int)(v1 - target) >= 0) break;
        v1 = ld_relaxed(p);
        if ((int)(v2 - target) >= 0) break;
        v2 = ld_relaxed(p);
        if ((int)(v3 - target) >= 0) break;
        if ((n & 15) == 15 && give_up(bar + B_ABORT, n, 1 << 21)) break;
    }
    flag_acquired();
}
__device__ __forceinline__ void flag_add(unsigned* p) { asm volatile("red.relaxed.gpu.global.add.u32 [%0], 1;" ::"l"(p) : "memory"); }
__device__ __forceinline__ void fence_async_smem() { asm volatile("fence.proxy.async.shared::cta;" ::: "memory"); }
__device__ __forceinline__ void bar_sync(int id, int n) { asm volatile("bar.sync %0, %1;" ::"r"(id), "r"(n) : "memory"); }
__device__ __forceinline__ void bar_arrive(int id, int n) { asm volatile("bar.arrive %0, %1;" ::"r"(id), "r"(n) : "memory"); }
__device__ __forceinline__ void bulk_g2s(uint32_t dst, const void* src, uint32_t bytes, uint32_t bar) {
    asm volatile("cp.async.bulk.shared::cluster.global.mbarrier::complete_tx::bytes [%0], [%1], %2, [%3];" ::"r"(dst), "l"(src), "r"(bytes), "r"(bar) : "memory");
}
__device__ __forceinline__ void bulk_s2g(void* dst, uint32_t src, uint32_t bytes) {
    asm volatile("cp.async.bulk.global.shared::cta.bulk_group [%0], [%1], %2;" ::"l"(dst), "r"(src), "r"(bytes) : "memory");
}
__device__ __forceinline__ void tma2(uint32_t dst, const CUtensorMap* m, int c0, int c1, uint32_t bar) {
    asm volatile("cp.async.bulk.tensor.2d.shared::cluster.global.mbarrier::complete_tx::bytes [%0], [%1, {%3, %4}], [%2];" ::"r"(dst), "l"(m), "r"(bar), "r"(c0), "r"(c1) : "memory");
}
__device__ __forceinline__ void tma3(uint32_t dst, const CUtensorMap* m, int c0, int c1, int c2, uint32_t bar) {
    asm volatile("cp.async.bulk.tensor.3d.shared::cluster.global.mbarrier::complete_tx::bytes [%0], [%1, {%3, %4, %5}], [%2];" ::"r"(dst), "l"(m), "r"(bar), "r"(c0), "r"(c1), "r"(c2) : "memory");
}
__device__ __forceinline__ uint4 ldx(const uint4* p) {
    uint4 v;
    asm volatile("ld.global.nc.L1::no_allocate.L2::256B.v4.u32 {%0,%1,%2,%3}, [%4];" : "=r"(v.x), "=r"(v.y), "=r"(v.z), "=r"(v.w) : "l"(p));
    return v;
}
__device__ __forceinline__ uint4 lds128(uint32_t a) { uint4 v; asm volatile("ld.shared.v4.u32 {%0,%1,%2,%3}, [%4];" : "=r"(v.x), "=r"(v.y), "=r"(v.z), "=r"(v.w) : "r"(a) : "memory"); return v; }
__device__ __forceinline__ void sts128(uint32_t a, uint4 v) { asm volatile("st.shared.v4.u32 [%4], {%0,%1,%2,%3};" ::"r"(v.x), "r"(v.y), "r"(v.z), "r"(v.w), "r"(a) : "memory"); }
__device__ __forceinline__ void sts32(uint32_t a, uint32_t v) { asm volatile("st.shared.u32 [%0], %1;" ::"r"(a), "r"(v) : "memory"); }
__device__ __forceinline__ void bulk_commit() { asm volatile("cp.async.bulk.commit_group;" ::: "memory"); }
__device__ __forceinline__ void bulk_wait_read() { asm volatile("cp.async.bulk.wait_group.read 0;" ::: "memory"); }
__device__ __forceinline__ void bulk_wait() { asm volatile("cp.async.bulk.wait_group 0;" ::: "memory"); }
__device__ __forceinline__ void ldsm4(uint32_t a, uint32_t (&r)[4]) {
    asm volatile("ldmatrix.sync.aligned.m8n8.x4.shared.b16 {%0,%1,%2,%3}, [%4];" : "=r"(r[0]), "=r"(r[1]), "=r"(r[2]), "=r"(r[3]) : "r"(a) : "memory");
}
__device__ __forceinline__ void ldsm4t(uint32_t a, uint32_t (&r)[4]) {
    asm volatile("ldmatrix.sync.aligned.m8n8.x4.trans.shared.b16 {%0,%1,%2,%3}, [%4];" : "=r"(r[0]), "=r"(r[1]), "=r"(r[2]), "=r"(r[3]) : "r"(a) : "memory");
}
__device__ __forceinline__ void mma16816(float* d, const uint32_t (&a)[4], uint32_t b0, uint32_t b1) {
    asm volatile("mma.sync.aligned.m16n8k16.row.col.f32.bf16.bf16.f32 {%0,%1,%2,%3}, {%4,%5,%6,%7}, {%8,%9}, {%0,%1,%2,%3};"
                 : "+f"(d[0]), "+f"(d[1]), "+f"(d[2]), "+f"(d[3]) : "r"(a[0]), "r"(a[1]), "r"(a[2]), "r"(a[3]), "r"(b0), "r"(b1));
}
__device__ __forceinline__ void stsm4(uint32_t a, uint32_t r0, uint32_t r1, uint32_t r2, uint32_t r3) {
    asm volatile("stmatrix.sync.aligned.m8n8.x4.shared.b16 [%0], {%1,%2,%3,%4};" ::"r"(a), "r"(r0), "r"(r1), "r"(r2), "r"(r3) : "memory");
}
__device__ __forceinline__ uint32_t pack2(float lo, float hi) { uint32_t r; asm("cvt.rn.bf16x2.f32 %0, %1, %2;" : "=r"(r) : "f"(hi), "f"(lo)); return r; }
__device__ __forceinline__ uint32_t pack2_relu(float lo, float hi) { uint32_t r; asm("cvt.rn.relu.bf16x2.f32 %0, %1, %2;" : "=r"(r) : "f"(hi), "f"(lo)); return r; }
__device__ __forceinline__ float bf_lo(uint32_t v) { return __uint_as_float(v << 16); }
__device__ __forceinline__ float bf_hi(uint32_t v) { return __uint_as_float(v & 0xffff0000u); }
__device__ __forceinline__ float ex2(float x) { float r; asm("ex2.approx.ftz.f32 %0, %1;" : "=f"(r) : "f"(x)); return r; }
__device__ __forceinline__ float sqrt_fast(float x) { float r; asm("sqrt.approx.f32 %0, %1;" : "=f"(r) : "f"(x)); return r; }
__device__ __forceinline__ float rcp_fast(float x) { float r; asm("rcp.approx.ftz.f32 %0, %1;" : "=f"(r) : "f"(x)); return r; }
__device__ __forceinline__ uint64_t mkdesc(uint32_t addr, uint32_t lbo, uint32_t sbo, uint32_t swz) {
    return (uint64_t)((addr >> 4) | ((lbo >> 4) << 16)) | ((uint64_t)((sbo >> 4) | (swz << 30)) << 32);
}

__device__ __forceinline__ void wg_ss(float (&d)[32], uint64_t da, uint64_t db, bool accumulate = true) {
    asm volatile("{\n.reg .pred p;\nsetp.ne.u32 p, %34, 0;\n"
                 "wgmma.mma_async.sync.aligned.m64n64k16.f32.bf16.bf16 {%0, %1, %2, %3, %4, %5, %6, %7, %8, %9, %10, %11, %12, %13, %14, %15, %16, %17, %18, %19, %20, %21, %22, %23, %24, %25, %26, %27, %28, %29, %30, %31}, %32, %33, p, 1, 1, 0, 1;\n}"
        : "+f"(d[0]), "+f"(d[1]), "+f"(d[2]), "+f"(d[3]), "+f"(d[4]), "+f"(d[5]), "+f"(d[6]), "+f"(d[7]), "+f"(d[8]), "+f"(d[9]), "+f"(d[10]), "+f"(d[11]), "+f"(d[12]), "+f"(d[13]), "+f"(d[14]), "+f"(d[15]), "+f"(d[16]), "+f"(d[17]), "+f"(d[18]), "+f"(d[19]), "+f"(d[20]), "+f"(d[21]), "+f"(d[22]), "+f"(d[23]), "+f"(d[24]), "+f"(d[25]), "+f"(d[26]), "+f"(d[27]), "+f"(d[28]), "+f"(d[29]), "+f"(d[30]), "+f"(d[31])
        : "l"(da), "l"(db), "r"((uint32_t)accumulate));
}
__device__ __forceinline__ void wg_ss(float (&d)[64], uint64_t da, uint64_t db, bool accumulate = true) {
    asm volatile("{\n.reg .pred p;\nsetp.ne.u32 p, %66, 0;\n"
                 "wgmma.mma_async.sync.aligned.m64n128k16.f32.bf16.bf16 {%0, %1, %2, %3, %4, %5, %6, %7, %8, %9, %10, %11, %12, %13, %14, %15, %16, %17, %18, %19, %20, %21, %22, %23, %24, %25, %26, %27, %28, %29, %30, %31, %32, %33, %34, %35, %36, %37, %38, %39, %40, %41, %42, %43, %44, %45, %46, %47, %48, %49, %50, %51, %52, %53, %54, %55, %56, %57, %58, %59, %60, %61, %62, %63}, %64, %65, p, 1, 1, 0, 1;\n}"
        : "+f"(d[0]), "+f"(d[1]), "+f"(d[2]), "+f"(d[3]), "+f"(d[4]), "+f"(d[5]), "+f"(d[6]), "+f"(d[7]), "+f"(d[8]), "+f"(d[9]), "+f"(d[10]), "+f"(d[11]), "+f"(d[12]), "+f"(d[13]), "+f"(d[14]), "+f"(d[15]), "+f"(d[16]), "+f"(d[17]), "+f"(d[18]), "+f"(d[19]), "+f"(d[20]), "+f"(d[21]), "+f"(d[22]), "+f"(d[23]), "+f"(d[24]), "+f"(d[25]), "+f"(d[26]), "+f"(d[27]), "+f"(d[28]), "+f"(d[29]), "+f"(d[30]), "+f"(d[31]), "+f"(d[32]), "+f"(d[33]), "+f"(d[34]), "+f"(d[35]), "+f"(d[36]), "+f"(d[37]), "+f"(d[38]), "+f"(d[39]), "+f"(d[40]), "+f"(d[41]), "+f"(d[42]), "+f"(d[43]), "+f"(d[44]), "+f"(d[45]), "+f"(d[46]), "+f"(d[47]), "+f"(d[48]), "+f"(d[49]), "+f"(d[50]), "+f"(d[51]), "+f"(d[52]), "+f"(d[53]), "+f"(d[54]), "+f"(d[55]), "+f"(d[56]), "+f"(d[57]), "+f"(d[58]), "+f"(d[59]), "+f"(d[60]), "+f"(d[61]), "+f"(d[62]), "+f"(d[63])
        : "l"(da), "l"(db), "r"((uint32_t)accumulate));
}
__device__ __forceinline__ void wg_ss(float (&d)[80], uint64_t da, uint64_t db, bool accumulate = true) {
    asm volatile("{\n.reg .pred p;\nsetp.ne.u32 p, %82, 0;\n"
                 "wgmma.mma_async.sync.aligned.m64n160k16.f32.bf16.bf16 {%0, %1, %2, %3, %4, %5, %6, %7, %8, %9, %10, %11, %12, %13, %14, %15, %16, %17, %18, %19, %20, %21, %22, %23, %24, %25, %26, %27, %28, %29, %30, %31, %32, %33, %34, %35, %36, %37, %38, %39, %40, %41, %42, %43, %44, %45, %46, %47, %48, %49, %50, %51, %52, %53, %54, %55, %56, %57, %58, %59, %60, %61, %62, %63, %64, %65, %66, %67, %68, %69, %70, %71, %72, %73, %74, %75, %76, %77, %78, %79}, %80, %81, p, 1, 1, 0, 1;\n}"
        : "+f"(d[0]), "+f"(d[1]), "+f"(d[2]), "+f"(d[3]), "+f"(d[4]), "+f"(d[5]), "+f"(d[6]), "+f"(d[7]), "+f"(d[8]), "+f"(d[9]), "+f"(d[10]), "+f"(d[11]), "+f"(d[12]), "+f"(d[13]), "+f"(d[14]), "+f"(d[15]), "+f"(d[16]), "+f"(d[17]), "+f"(d[18]), "+f"(d[19]), "+f"(d[20]), "+f"(d[21]), "+f"(d[22]), "+f"(d[23]), "+f"(d[24]), "+f"(d[25]), "+f"(d[26]), "+f"(d[27]), "+f"(d[28]), "+f"(d[29]), "+f"(d[30]), "+f"(d[31]), "+f"(d[32]), "+f"(d[33]), "+f"(d[34]), "+f"(d[35]), "+f"(d[36]), "+f"(d[37]), "+f"(d[38]), "+f"(d[39]), "+f"(d[40]), "+f"(d[41]), "+f"(d[42]), "+f"(d[43]), "+f"(d[44]), "+f"(d[45]), "+f"(d[46]), "+f"(d[47]), "+f"(d[48]), "+f"(d[49]), "+f"(d[50]), "+f"(d[51]), "+f"(d[52]), "+f"(d[53]), "+f"(d[54]), "+f"(d[55]), "+f"(d[56]), "+f"(d[57]), "+f"(d[58]), "+f"(d[59]), "+f"(d[60]), "+f"(d[61]), "+f"(d[62]), "+f"(d[63]), "+f"(d[64]), "+f"(d[65]), "+f"(d[66]), "+f"(d[67]), "+f"(d[68]), "+f"(d[69]), "+f"(d[70]), "+f"(d[71]), "+f"(d[72]), "+f"(d[73]), "+f"(d[74]), "+f"(d[75]), "+f"(d[76]), "+f"(d[77]), "+f"(d[78]), "+f"(d[79])
        : "l"(da), "l"(db), "r"((uint32_t)accumulate));
}
__device__ __forceinline__ void wg_rs_acc_n24(float (&d)[12], uint32_t a0, uint32_t a1, uint32_t a2, uint32_t a3, uint64_t db) {
    asm volatile("wgmma.mma_async.sync.aligned.m64n24k16.f32.bf16.bf16 {%0, %1, %2, %3, %4, %5, %6, %7, %8, %9, %10, %11}, {%12, %13, %14, %15}, %16, 1, 1, 1, 1;"
        : "+f"(d[0]), "+f"(d[1]), "+f"(d[2]), "+f"(d[3]), "+f"(d[4]), "+f"(d[5]), "+f"(d[6]), "+f"(d[7]), "+f"(d[8]), "+f"(d[9]), "+f"(d[10]), "+f"(d[11])
        : "r"(a0), "r"(a1), "r"(a2), "r"(a3), "l"(db));
}
__device__ __forceinline__ void wg_rs_init_n64(float (&d)[32], const uint32_t (&a)[4], uint64_t db) {
    asm volatile("wgmma.mma_async.sync.aligned.m64n64k16.f32.bf16.bf16 {%0, %1, %2, %3, %4, %5, %6, %7, %8, %9, %10, %11, %12, %13, %14, %15, %16, %17, %18, %19, %20, %21, %22, %23, %24, %25, %26, %27, %28, %29, %30, %31}, {%32, %33, %34, %35}, %36, 0, 1, 1, 0;"
        : "=f"(d[0]), "=f"(d[1]), "=f"(d[2]), "=f"(d[3]), "=f"(d[4]), "=f"(d[5]), "=f"(d[6]), "=f"(d[7]), "=f"(d[8]), "=f"(d[9]), "=f"(d[10]), "=f"(d[11]), "=f"(d[12]), "=f"(d[13]), "=f"(d[14]), "=f"(d[15]), "=f"(d[16]), "=f"(d[17]), "=f"(d[18]), "=f"(d[19]), "=f"(d[20]), "=f"(d[21]), "=f"(d[22]), "=f"(d[23]), "=f"(d[24]), "=f"(d[25]), "=f"(d[26]), "=f"(d[27]), "=f"(d[28]), "=f"(d[29]), "=f"(d[30]), "=f"(d[31])
        : "r"(a[0]), "r"(a[1]), "r"(a[2]), "r"(a[3]), "l"(db));
}
__device__ __forceinline__ void wg_rs_acc_n64(float (&d)[32], uint32_t a0, uint32_t a1, uint32_t a2, uint32_t a3, uint64_t db) {
    asm volatile("wgmma.mma_async.sync.aligned.m64n64k16.f32.bf16.bf16 {%0, %1, %2, %3, %4, %5, %6, %7, %8, %9, %10, %11, %12, %13, %14, %15, %16, %17, %18, %19, %20, %21, %22, %23, %24, %25, %26, %27, %28, %29, %30, %31}, {%32, %33, %34, %35}, %36, 1, 1, 1, 0;"
        : "+f"(d[0]), "+f"(d[1]), "+f"(d[2]), "+f"(d[3]), "+f"(d[4]), "+f"(d[5]), "+f"(d[6]), "+f"(d[7]), "+f"(d[8]), "+f"(d[9]), "+f"(d[10]), "+f"(d[11]), "+f"(d[12]), "+f"(d[13]), "+f"(d[14]), "+f"(d[15]), "+f"(d[16]), "+f"(d[17]), "+f"(d[18]), "+f"(d[19]), "+f"(d[20]), "+f"(d[21]), "+f"(d[22]), "+f"(d[23]), "+f"(d[24]), "+f"(d[25]), "+f"(d[26]), "+f"(d[27]), "+f"(d[28]), "+f"(d[29]), "+f"(d[30]), "+f"(d[31])
        : "r"(a0), "r"(a1), "r"(a2), "r"(a3), "l"(db));
}
__device__ __forceinline__ void wg_rs_acc_n64(float (&d)[32], const uint32_t (&a)[4], uint64_t db) { wg_rs_acc_n64(d, a[0], a[1], a[2], a[3], db); }

constexpr float EXP2_C3 = 0.0551716685295105f * 0x1p-59f;
__device__ __forceinline__ float exp2_fma(float u, float c3) {
    float t, f;
    asm("mul.rn.sat.f32 %0, %1, 0f00400000;" : "=f"(t) : "f"(u));
    asm("fma.rn.f32 %0, %1, 0fFF000000, %2;" : "=f"(f) : "f"(t), "f"(u));
    float p = fmaf(f, c3, 0.2426111400127411f * 0x1p-81f);
    p = fmaf(p, f, 0.6932609677314758f * 0x1p-103f);
    p = fmaf(p, f, 0.9999280571937561f * 0x1p-125f);
    return __uint_as_float(__float_as_uint(p) + (__float_as_uint(t) << 23));
}
template <uint32_t PM8>
__device__ __forceinline__ void sm_level(const float* S, uint32_t* P, float c3) {
    float r[8];
#pragma unroll
    for (int i = 0; i < 8; i++) r[i] = ((PM8 >> i) & 1) ? exp2_fma(S[i], c3) : ex2(S[i]);
#pragma unroll
    for (int i = 0; i < 4; i++) P[i] = pack2(r[2 * i], r[2 * i + 1]);
}

__device__ __forceinline__ uint64_t kvdesc(uint32_t lo) { return ((uint64_t)(256 >> 4) << 32) | lo; }

__device__ __forceinline__ void row_norm2(const uint32_t (&q)[4], float& n0, float& n1) {
    float a = bf_lo(q[0]), b = bf_hi(q[0]), c = bf_lo(q[2]), d = bf_hi(q[2]);
    n0 = a * a + b * b + c * c + d * d;
    a = bf_lo(q[1]); b = bf_hi(q[1]); c = bf_lo(q[3]); d = bf_hi(q[3]);
    n1 = a * a + b * b + c * c + d * d;
    n0 += __shfl_xor_sync(0xffffffffu, n0, 1); n1 += __shfl_xor_sync(0xffffffffu, n1, 1);
    n0 += __shfl_xor_sync(0xffffffffu, n0, 2); n1 += __shfl_xor_sync(0xffffffffu, n1, 2);
}
__device__ __forceinline__ void row_norm(const uint32_t (&q)[4], float& n0, float& n1) {
    row_norm2(q, n0, n1);
    n0 = sqrt_fast(n0); n1 = sqrt_fast(n1);
}
__device__ __forceinline__ float row_shift(float qn, float kp) {
    const float ub = fmaf(qn * kp, 1.0078125f, 1.0f);
    const float m0 = ceilf(fmaxf(ub - 126.0f, 0.8f * ub - 18.0f));
    return m0 > 128.0f ? __uint_as_float((__float_as_uint(m0) + 0xffffu) & 0xffff0000u) : m0;
}
__device__ __forceinline__ float row_lmin(float qn, float m0, float kp, float vfloor) {
    const float ub = fmaf(qn * kp, 1.0078125f, 1.0f);
    const float F = fmaxf(ub + m0 - 124.0f, 0.0f) + 1.0f;
    const float lmin = fmaxf(0x1p-90f * (2.0f + F * F * F * 0.125f), vfloor);
    return ((ub - m0 <= 127.0f) & (ub <= 1.0e30f)) ? lmin : INFINITY;
}

__device__ __forceinline__ void shift_fragment(uint32_t (&qa)[4], float m0, float m1, int lane, uint32_t zero_addr) {
    qa[0] = (lane & 3) ? 0u : pack2(-m0, 1.0f); qa[1] = (lane & 3) ? 0u : pack2(-m1, 1.0f);
    asm volatile("ld.shared.v2.u32 {%0, %1}, [%2];" : "=r"(qa[2]), "=r"(qa[3]) : "r"(zero_addr) : "memory");
    pin(qa);
}
__device__ __forceinline__ void load_stats(uint32_t sb, int lane, float& kp, float& vfloor) {
    mbar_wait(sb + OFF_BAR + B_ST, 0);
    uint32_t a = 0, b = 0;
#pragma unroll
    for (int i = 0; i < 4; i++) {
        uint32_t u, v;
        asm volatile("ld.shared.v2.u32 {%0, %1}, [%2];" : "=r"(u), "=r"(v) : "r"(sb + OFF_OS + (i * 32 + lane) * 32) : "memory");
        a = max(a, u); b = max(b, v);
    }
    kp = sqrt_fast(__uint_as_float(__reduce_max_sync(0xffffffffu, a)));
    const float vmax = __uint_as_float(__reduce_max_sync(0xffffffffu, b));
    vfloor = vmax != 0.0f ? 0x1p-90f * rcp_fast(fmaxf(vmax, 0x1p-120f)) : 0.0f;
}

__device__ __forceinline__ void attn_exact(const uint32_t q0, const uint32_t q1, const uint32_t q2, const uint32_t q3, float* res, int lane) {
    const int g = lane >> 2, c = lane & 3;
    float o[2][4] = {{0.f, 0.f, 0.f, 0.f}, {0.f, 0.f, 0.f, 0.f}};
    float m0 = -INFINITY, m1 = -INFINITY, l0 = 0.f, l1 = 0.f;
#pragma unroll 1
    for (int kb = 0; kb < 128; kb++) {
        const uint8_t* st = g_kv + (kb >> 3) * KV_SLOT;
        float s[2][4];
#pragma unroll
        for (int nt = 0; nt < 2; nt++) {
            const uint8_t* kp = st + ((kb & 7) * 2 + nt) * 256 + g * 16 + c * 4;
            const uint32_t b0 = __ldcg((const uint32_t*)kp), b1 = __ldcg((const uint32_t*)(kp + 128));
            asm volatile("mma.sync.aligned.m16n8k16.row.col.f32.bf16.bf16.f32 {%0,%1,%2,%3}, {%4,%5,%6,%7}, {%8,%9}, {%10,%10,%10,%10};"
                         : "=f"(s[nt][0]), "=f"(s[nt][1]), "=f"(s[nt][2]), "=f"(s[nt][3])
                         : "r"(q0), "r"(q1), "r"(q2), "r"(q3), "r"(b0), "r"(b1), "f"(0.f));
#pragma unroll
            for (int i = 0; i < 4; i++) s[nt][i] *= (!(i & 1) && ((PM_POLY >> (8 * (kb & 3) + 4 * nt)) & 1)) ? 0x1p22f : 1.0f;
        }
        float x0 = fmaxf(fmaxf(s[0][0], s[0][1]), fmaxf(s[1][0], s[1][1])), x1 = fmaxf(fmaxf(s[0][2], s[0][3]), fmaxf(s[1][2], s[1][3]));
        x0 = fmaxf(x0, __shfl_xor_sync(0xffffffffu, x0, 1)); x1 = fmaxf(x1, __shfl_xor_sync(0xffffffffu, x1, 1));
        x0 = fmaxf(x0, __shfl_xor_sync(0xffffffffu, x0, 2)); x1 = fmaxf(x1, __shfl_xor_sync(0xffffffffu, x1, 2));
        const float n0 = fmaxf(m0, x0), n1 = fmaxf(m1, x1);
        const float a0 = ex2(m0 - n0), a1 = ex2(m1 - n1);
        m0 = n0; m1 = n1;
        uint32_t p[4];
        p[0] = pack2(ex2(s[0][0] - n0), ex2(s[0][1] - n0)); p[1] = pack2(ex2(s[0][2] - n1), ex2(s[0][3] - n1));
        p[2] = pack2(ex2(s[1][0] - n0), ex2(s[1][1] - n0)); p[3] = pack2(ex2(s[1][2] - n1), ex2(s[1][3] - n1));
        l0 = l0 * a0 + (bf_lo(p[0]) + bf_hi(p[0]) + bf_lo(p[2]) + bf_hi(p[2]));
        l1 = l1 * a1 + (bf_lo(p[1]) + bf_hi(p[1]) + bf_lo(p[3]) + bf_hi(p[3]));
#pragma unroll
        for (int dt = 0; dt < 2; dt++) {
            const uint8_t* vp = st + 4096 + (kb & 7) * 768 + dt * 256 + c * 32 + g * 2;
            const uint32_t b0 = (uint32_t)__ldcg((const unsigned short*)vp) | ((uint32_t)__ldcg((const unsigned short*)(vp + 16)) << 16);
            const uint32_t b1 = (uint32_t)__ldcg((const unsigned short*)(vp + 128)) | ((uint32_t)__ldcg((const unsigned short*)(vp + 144)) << 16);
            o[dt][0] *= a0; o[dt][1] *= a0; o[dt][2] *= a1; o[dt][3] *= a1;
            asm volatile("mma.sync.aligned.m16n8k16.row.col.f32.bf16.bf16.f32 {%0,%1,%2,%3}, {%4,%5,%6,%7}, {%8,%9}, {%0,%1,%2,%3};"
                         : "+f"(o[dt][0]), "+f"(o[dt][1]), "+f"(o[dt][2]), "+f"(o[dt][3])
                         : "r"(p[0]), "r"(p[1]), "r"(p[2]), "r"(p[3]), "r"(b0), "r"(b1));
        }
    }
    l0 += __shfl_xor_sync(0xffffffffu, l0, 1); l1 += __shfl_xor_sync(0xffffffffu, l1, 1);
    l0 += __shfl_xor_sync(0xffffffffu, l0, 2); l1 += __shfl_xor_sync(0xffffffffu, l1, 2);
    const float i0 = 1.0f / l0, i1 = 1.0f / l1;
    res[0] = o[0][0] * i0; res[1] = o[0][1] * i0; res[2] = o[0][2] * i1; res[3] = o[0][3] * i1;
    res[4] = o[1][0] * i0; res[5] = o[1][1] * i0; res[6] = o[1][2] * i1; res[7] = o[1][3] * i1;
}

__device__ __forceinline__ void attention_role(const uint32_t sb, const int wg, const int warp, const int lane, const int ti, const int tj) {
    const uint32_t bar = sb + OFF_BAR;
    const int tid = warp * 32 + lane;
    uint32_t q[2][4];
    {
        bar_sync(1, 384);
        mbar_wait(bar + B_WQ1, 0);
        float full[32], acc[16];
        pin(full);
        const uint64_t da = mkdesc(sb + OFF_XN + wg * 32768, 16, 1024, 1), db = mkdesc(sb + OFF_WQ1 + wg * 32768, 16, 1024, 1);
        wg_fence();
#pragma unroll
        for (int kc = 0; kc < 4; kc++)
#pragma unroll
            for (int ks = 0; ks < 4; ks++) wg_ss(full, da + (uint64_t)(kc * 512 + ks * 2), db + (uint64_t)((kc * 4 + ks) * 128), ks > 0 || kc > 0);
        wg_commit();
        wg_wait<0>();
        pin(full);
#pragma unroll
        for (int i = 0; i < 4; i++) {
            const float x0 = wg ? full[4 * i] : full[16 + 4 * i], x1 = wg ? full[4 * i + 1] : full[17 + 4 * i], x2 = wg ? full[4 * i + 2] : full[18 + 4 * i], x3 = wg ? full[4 * i + 3] : full[19 + 4 * i];
            sts128(sb + OFF_WKV + wg * 8192 + i * 2048 + tid * 16, make_uint4(__float_as_uint(x0), __float_as_uint(x1), __float_as_uint(x2), __float_as_uint(x3)));
        }
        bar_sync(6, 256);
#pragma unroll
        for (int i = 0; i < 4; i++) {
            const uint4 v = lds128(sb + OFF_WKV + (wg ^ 1) * 8192 + i * 2048 + tid * 16);
            acc[4 * i] = __uint_as_float(v.x) + (wg ? full[16 + 4 * i] : full[4 * i]); acc[4 * i + 1] = __uint_as_float(v.y) + (wg ? full[17 + 4 * i] : full[4 * i + 1]);
            acc[4 * i + 2] = __uint_as_float(v.z) + (wg ? full[18 + 4 * i] : full[4 * i + 2]); acc[4 * i + 3] = __uint_as_float(v.w) + (wg ? full[19 + 4 * i] : full[4 * i + 3]);
        }
        constexpr float QS = 0.25f * 1.4426950408889634f;
#pragma unroll
        for (int t = 0; t < 2; t++)
#pragma unroll
            for (int i = 0; i < 4; i++) q[t][i] = pack2(acc[8 * t + 2 * i] * QS, acc[8 * t + 2 * i + 1] * QS);
    }
    const uint32_t dbase = ((128 >> 4) << 16) | ((sb + OFF_KV) >> 4);
    const uint64_t daug = kvdesc(((128 >> 4) << 16) | ((sb + OFF_AUG) >> 4));
    float qn[2][2], m0[2][2], Oa[2][12], S[2][32];
    uint32_t P[2][16], qa[2][4];
    {
        float kest;
        asm volatile("ld.shared.f32 %0, [%1];" : "=f"(kest) : "r"(bar + B_KEST) : "memory");
#pragma unroll
        for (int t = 0; t < 2; t++) {
            row_norm(q[t], qn[t][0], qn[t][1]);
            m0[t][0] = row_shift(qn[t][0], kest); m0[t][1] = row_shift(qn[t][1], kest);
            shift_fragment(qa[t], m0[t][0], m0[t][1], lane, sb + OFF_AUG + 128);
        }
        mbar_wait(bar + B_KVF, 0);
        wg_fence();
        wg_rs_init_n64(S[0], q[0], kvdesc(dbase));
        wg_rs_acc_n64(S[0], qa[0], daug);
        wg_commit();
        fence_async_smem();
        __syncwarp();
        if (lane == 0) mbar_arrive(bar + B_PRO);
        wg_wait<0>();
        pin(S[0]);
    }
    float c3;
    asm volatile("ld.shared.f32 %0, [%1];" : "=f"(c3) : "r"(bar + B_KEST + 4) : "memory");
    uint32_t it = 0;
#pragma unroll 1
    for (int round = 0; round < 2; round++) {
#pragma unroll
        for (int t = 0; t < 2; t++) {
#pragma unroll
            for (int i = 0; i < 12; i++) Oa[t][i] = 0.f;
            pin(Oa[t]);
        }
        mbar_wait(bar + B_KVF + 8 * ((it + 1) & (NKV - 1)), ((it + 1) / NKV) & 1);
#pragma unroll 1
        for (;;) {
            uint32_t go = 0;
            const uint32_t k0 = dbase + (it & (NKV - 1)) * (KV_SLOT >> 4);
            const uint32_t v0 = k0 + (4096 >> 4);
            const uint32_t kn = dbase + ((it + 1) & (NKV - 1)) * (KV_SLOT >> 4);
            wg_fence();
            wg_rs_init_n64(S[1], q[1], kvdesc(k0));
            wg_rs_acc_n64(S[1], qa[1], daug);
            wg_commit();
#pragma unroll
            for (int s = 0; s < 4; s++) {
                const int b = s & 1, nb = b ^ 1, hb = s >> 1;
#pragma unroll
                for (int k = 0; k < 4; k++) {
                    if (k == 0) sm_level<(PM_POLY >> 0) & 0xff>(&S[b][0], &P[b][0], c3);
                    if (k == 1) sm_level<(PM_POLY >> 8) & 0xff>(&S[b][8], &P[b][4], c3);
                    if (k == 2) sm_level<(PM_POLY >> 16) & 0xff>(&S[b][16], &P[b][8], c3);
                    if (k == 3) sm_level<(PM_POLY >> 24) & 0xff>(&S[b][24], &P[b][12], c3);
                    pin4(&P[b][4 * k]);
                    wg_fence();
                    if (s == 0 && k == 3) {
                        if (lane == 0) mbar_arrive(bar + B_KVE + 8 * ((it + NKV - 1) & (NKV - 1)));
                        go = mbar_test(bar + B_KVF + 8 * ((it + 2) & (NKV - 1)), ((it + 2) / NKV) & 1);
                        if ((it & 15) == 15) go = 0;
                    }
                    if (k == 3 && s < 3) wg_rs_init_n64(S[b], qa[b], daug);
                    wg_rs_acc_n24(Oa[b], P[b][4 * k], P[b][4 * k + 1], P[b][4 * k + 2], P[b][4 * k + 3], kvdesc(v0 + (hb * 4 + k) * (768 >> 4)));
                    if (k == 3 && s < 3) wg_rs_acc_n64(S[b], q[b], kvdesc(s == 2 ? kn : k0 + (2048 >> 4)));
                    wg_commit();
                    if (k == 1) { wg_wait<2>(); pin(S[nb]); pin(P[nb]); }
                }
            }
            it++;
            if (go) continue;
            if ((it & 15) == 0) break;
            if (it + 1 < 32) mbar_wait(bar + B_KVF + 8 * ((it + 1) & (NKV - 1)), ((it + 1) / NKV) & 1);
        }
        float r[2][8], lmin[2][2];
        bool good[2];
        {
            float kp, vfloor;
            mbar_wait(bar + (round ? B_OE : B_Q2), 0);
            asm volatile("ld.shared.v2.f32 {%0, %1}, [%2];" : "=f"(kp), "=f"(vfloor) : "r"(bar + B_STAT) : "memory");
#pragma unroll
            for (int t = 0; t < 2; t++) { lmin[t][0] = row_lmin(qn[t][0], m0[t][0], kp, vfloor); lmin[t][1] = row_lmin(qn[t][1], m0[t][1], kp, vfloor); }
            pin(lmin[0]); pin(lmin[1]);
        }
        wg_wait<0>();
        pin(S[0]); pin(Oa[0]); pin(Oa[1]);
#pragma unroll
        for (int t = 0; t < 2; t++) {
            const float l0 = __shfl_sync(0xffffffffu, Oa[t][8], lane & ~3), l1 = __shfl_sync(0xffffffffu, Oa[t][10], lane & ~3);
            const float i0 = rcp_fast(l0), i1 = rcp_fast(l1);
            uint32_t big = 0;
#pragma unroll
            for (int i = 0; i < 8; i++) { big = max(big, __float_as_uint(Oa[t][i]) & 0x7fffffffu); r[t][i] = Oa[t][i] * ((i & 2) ? i1 : i0); }
            good[t] = (l0 >= lmin[t][0]) & (l1 >= lmin[t][1]) & (l0 <= 0x1p125f) & (l1 <= 0x1p125f) & (big < 0x7f800000u);
        }
        if (!__all_sync(0xffffffffu, good[0] & good[1])) {
#pragma unroll 1
            for (int t = 0; t < 2; t++) {
                if (__all_sync(0xffffffffu, t ? good[1] : good[0])) continue;
                float res[8];
                attn_exact(t ? q[1][0] : q[0][0], t ? q[1][1] : q[0][1], t ? q[1][2] : q[0][2], t ? q[1][3] : q[0][3], res, lane);
#pragma unroll
                for (int i = 0; i < 8; i++) { if (t) r[1][i] = res[i]; else r[0][i] = res[i]; }
            }
        }
        const uint32_t op = sb + OFF_OS + wg * 4096;
        const int r0 = warp * 16 + (lane >> 2), sw = (r0 >> 1) & 3;
        const uint32_t p0 = op + r0 * 64 + (lane & 3) * 4;
        auto stage_out = [&]() {
#pragma unroll
            for (int t = 0; t < 2; t++) {
                sts32(p0 + (((2 * t) ^ sw) << 4), pack2(r[t][0], r[t][1]));
                sts32(p0 + (((2 * t + 1) ^ sw) << 4), pack2(r[t][4], r[t][5]));
                sts32(p0 + 512 + (((2 * t) ^ sw) << 4), pack2(r[t][2], r[t][3]));
                sts32(p0 + 512 + (((2 * t + 1) ^ sw) << 4), pack2(r[t][6], r[t][7]));
            }
        };
        if (round == 1) {
            stage_out();
            fence_async_smem();
            __syncwarp();
            if (lane == 0) {
                bulk_s2g(g_o + (size_t)(ti * 16 + tj * 4 + 2 + wg) * 4096 + warp * 1024, op + warp * 1024, 1024);
                bulk_commit();
                mbar_arrive(bar + B_OR + 8);
                bulk_wait();
                flag_add(&g_sync[SY_O + (ti * 2 + 1) * 32]);
            }
            break;
        }
#pragma unroll
        for (int t = 0; t < 2; t++) {
            const uint4 v = lds128(sb + OFF_Q2 + (wg * 2 + t) * 2048 + tid * 16);
            q[t][0] = v.x; q[t][1] = v.y; q[t][2] = v.z; q[t][3] = v.w;
            const uint32_t a = sb + OFF_QM + ((wg * 2 + t) * 64 + r0) * 8;
            asm volatile("ld.shared.v2.f32 {%0, %1}, [%2];" : "=f"(m0[t][0]), "=f"(qn[t][0]) : "r"(a) : "memory");
            asm volatile("ld.shared.v2.f32 {%0, %1}, [%2];" : "=f"(m0[t][1]), "=f"(qn[t][1]) : "r"(a + 64) : "memory");
            shift_fragment(qa[t], m0[t][0], m0[t][1], lane, sb + OFF_AUG + 128);
            pin(q[t]);
        }
        wg_fence();
        wg_rs_init_n64(S[0], q[0], kvdesc(dbase + (it & (NKV - 1)) * (KV_SLOT >> 4)));
        wg_rs_acc_n64(S[0], qa[0], daug);
        wg_commit();
        stage_out();
        fence_async_smem();
        __syncwarp();
        if (lane == 0) mbar_arrive(bar + B_OR);
        wg_wait<0>();
        pin(S[0]);
    }
}

template <int N>
__device__ __forceinline__ void ffn1_pass(const uint32_t sb, const uint64_t dxn, uint32_t& gi, const int p, const int warp, const int lane) {
    const uint32_t bar = sb + OFF_BAR;
    float acc[N / 2];
    pin(acc);
#pragma unroll 1
    for (int kc = 0; kc < 8; kc++, gi++) {
        mbar_wait<NS_GC>(bar + B_GF + 8 * (gi & 3), (gi >> 2) & 1);
        const uint64_t db = mkdesc(sb + OFF_G + (gi & 3) * G_SLOT, 4096, 512, 2);
        wg_fence();
#pragma unroll
        for (int ks = 0; ks < 4; ks++) wg_ss(acc, dxn + (uint64_t)(kc * 512 + ks * 2), db + (uint64_t)(ks * 64), ks > 0 || kc > 0);
        wg_commit();
        wg_wait<1>();
        if (kc > 0 && lane == 0) mbar_arrive(bar + B_GE + 8 * ((gi - 1) & 3));
    }
    wg_wait<0>();
    pin(acc);
    bar_sync(2, 128);
    const int r = warp * 16 + ((lane >> 3) & 1) * 8 + (lane & 7);
    const uint32_t base = sb + OFF_G + 3 * G_SLOT + r * 64;
    const int sw = (r >> 1) & 3, uh = lane >> 4;
#pragma unroll
    for (int jb = 0; jb < N / 8; jb += 2) {
        uint32_t v[4];
#pragma unroll
        for (int i = 0; i < 4; i++) v[i] = pack2_relu(acc[4 * jb + 2 * i], acc[4 * jb + 2 * i + 1]);
        stsm4(base + (jb >> 2) * 4096 + ((((jb & 3) + uh) ^ sw) << 4), v[0], v[1], v[2], v[3]);
    }
    fence_async_smem();
    __syncwarp();
    if (lane == 0) mbar_arrive(bar + B_HR + 8 * p);
}

__device__ __forceinline__ void kv_projection(const uint32_t sb, const int warp, const int lane, const int ti, const int tj) {
    const uint32_t bar = sb + OFF_BAR;
    const int g = lane >> 2, c = lane & 3;
    {
        mbar_wait(bar + B_WKV, 0);
        float acc[16];
#pragma unroll
        for (int i = 0; i < 16; i++) acc[i] = 0.f;
        const int ra = tj * 16 + (lane & 15);
        const uint32_t abase = sb + OFF_XN + warp * 16384 + ra * 128;
        const uint32_t bbase = sb + OFF_WKV + (warp * 128 + (lane >> 4) * 8 + (lane & 7)) * 32 + ((((lane >> 2) ^ (lane >> 3)) & 1) << 4);
#pragma unroll
        for (int ks = 0; ks < 8; ks++) {
            uint32_t a[4], bk[4], bv[4];
            ldsm4(abase + (ks >> 2) * 8192 + ((((ks & 3) * 2 + (lane >> 4)) ^ (ra & 7)) << 4), a);
            ldsm4t(bbase + ks * 512, bk);
            ldsm4t(bbase + 16384 + ks * 512, bv);
            const bool lo = c < 2;
            mma16816(&acc[0], a, lo ? bk[0] : bk[1], lo ? bk[2] : bk[3]);
            mma16816(&acc[4], a, lo ? bk[1] : bk[0], lo ? bk[3] : bk[2]);
            mma16816(&acc[8], a, lo ? bv[0] : bv[1], lo ? bv[2] : bv[3]);
            mma16816(&acc[12], a, lo ? bv[1] : bv[0], lo ? bv[3] : bv[2]);
        }
        if (warp != 0) {
#pragma unroll
            for (int i = 0; i < 4; i++)
                sts128(sb + OFF_KV + (warp * 4 + i) * 512 + lane * 16, make_uint4(__float_as_uint(acc[4 * i]), __float_as_uint(acc[4 * i + 1]), __float_as_uint(acc[4 * i + 2]), __float_as_uint(acc[4 * i + 3])));
        }
        __syncwarp();
        if (lane == 0) mbar_arrive(bar + B_PRO);
        bar_sync(2, 128);
        if (warp != 0) bar_arrive(5, 512);
        if (warp == 0) {
#pragma unroll
            for (int w = 1; w < 4; w++)
#pragma unroll
                for (int i = 0; i < 4; i++) {
                    const uint4 v = lds128(sb + OFF_KV + (w * 4 + i) * 512 + lane * 16);
                    acc[4 * i] += __uint_as_float(v.x); acc[4 * i + 1] += __uint_as_float(v.y); acc[4 * i + 2] += __uint_as_float(v.z); acc[4 * i + 3] += __uint_as_float(v.w);
                }
            uint32_t kf[4], vf[4];
#pragma unroll
            for (int i = 0; i < 4; i++) { kf[i] = pack2(acc[2 * i], acc[2 * i + 1]); vf[i] = pack2(acc[8 + 2 * i], acc[8 + 2 * i + 1]); }
            float n0, n1;
            row_norm2(kf, n0, n1);
            const uint32_t u0 = (n0 == n0) ? __float_as_uint(n0) : 0x7fc00000u, u1 = (n1 == n1) ? __float_as_uint(n1) : 0x7fc00000u;
            int rk = 0;
#pragma unroll
            for (int h = 0; h < 2; h++) {
                const int r = c + 4 * h;
                const uint32_t a = __shfl_sync(0xffffffffu, u0, r * 4), b = __shfl_sync(0xffffffffu, u1, r * 4);
                rk += (a < u0 || (a == u0 && r < g)) + (b < u0) + (((a <= u1) + (b < u1 || (b == u1 && r < g))) << 8);
            }
            rk += __shfl_xor_sync(0xffffffffu, rk, 1);
            rk += __shfl_xor_sync(0xffffffffu, rk, 2);
            const int rk0 = rk & 0xff, rk1 = rk >> 8;
            const uint32_t pm = (PM_POLY >> (8 * tj)) & 0xff;
            const int np = ((pm & 0x0f) ? 4 : 0) + ((pm & 0xf0) ? 4 : 0), flip = (pm & 0x0f) ? 0 : 4;
            const int p0 = rk0 < 8 ? 2 * (rk0 ^ flip) : 2 * rk0 - 15, p1 = rk1 < 8 ? 2 * (rk1 ^ flip) : 2 * rk1 - 15;
            {
                const float s0 = rk0 < np ? 0x1p-22f : 1.0f, s1 = rk1 < np ? 0x1p-22f : 1.0f;
                kf[0] = pack2(bf_lo(kf[0]) * s0, bf_hi(kf[0]) * s0); kf[2] = pack2(bf_lo(kf[2]) * s0, bf_hi(kf[2]) * s0);
                kf[1] = pack2(bf_lo(kf[1]) * s1, bf_hi(kf[1]) * s1); kf[3] = pack2(bf_lo(kf[3]) * s1, bf_hi(kf[3]) * s1);
            }
            uint32_t kb2 = max(rk0 < np ? u0 : 0u, rk1 < np ? u1 : 0u), vm = 0;
#pragma unroll
            for (int i = 0; i < 4; i++) vm = max(vm, max((vf[i] << 16) & 0x7fffffffu, vf[i] & 0x7fff0000u));
            {
                float e = n0 + n1;
                e += __shfl_xor_sync(0xffffffffu, e, 4); e += __shfl_xor_sync(0xffffffffu, e, 8); e += __shfl_xor_sync(0xffffffffu, e, 16);
                if (lane == 0) { sts32(bar + B_KEST, __float_as_uint(sqrt_fast(e * (1.35f / 16.0f)))); sts32(bar + B_KEST + 4, __float_as_uint(EXP2_C3)); }
            }
            kb2 = __reduce_max_sync(0xffffffffu, kb2);
            vm = __reduce_max_sync(0xffffffffu, vm);
            const uint32_t stg = sb + OFF_Q2;
            const uint32_t k0p = stg + (p0 >> 3) * 256 + (p0 & 7) * 16 + c * 4, k1p = stg + (p1 >> 3) * 256 + (p1 & 7) * 16 + c * 4;
            sts32(k0p, kf[0]); sts32(k0p + 128, kf[2]); sts32(k1p, kf[1]); sts32(k1p + 128, kf[3]);
            const uint32_t v0p = stg + 512 + p0 * 16 + c * 4, v1p = stg + 512 + p1 * 16 + c * 4;
            sts32(v0p, vf[0]); sts32(v0p + 256, vf[2]); sts32(v1p, vf[1]); sts32(v1p + 256, vf[3]);
            if (lane < 16) sts128(stg + 1024 + lane * 16, make_uint4(0x3F80u, 0u, 0u, 0u));
            else if (lane < 18) sts128(stg + 1280 + (lane - 16) * 16, make_uint4(kb2, vm, 0u, 0u));
            fence_async_smem();
            __syncwarp();
            bar_arrive(5, 512);
            if (lane == 0) {
                uint8_t* dst = g_kv + (ti >> 1) * KV_SLOT;
                const int ks = (ti & 1) * 4 + tj;
                bulk_s2g(dst + ks * 512, stg, 512);
                bulk_s2g(dst + 4096 + ks * 768, stg + 512, 768);
                bulk_s2g(g_stats + (ti * 4 + tj) * 32, stg + 1280, 32);
                bulk_commit();
                bulk_wait();
                flag_add(&g_sync[SY_KV + (ti >> 1) * 32]);
            }
            __syncwarp();
            uint32_t epoch;
            asm volatile("ld.shared.u32 %0, [%1];" : "=r"(epoch) : "r"(bar + B_EPOCH) : "memory");
            const uint32_t s0 = ti >> 1, target = (epoch + 1) * 8u;
            const unsigned* fp = &g_sync[SY_KV + ((lane + s0) & 15) * 32];
            uint32_t next = 0, v0 = ld_relaxed(fp);
            __nanosleep(100);
#pragma unroll 1
            for (int n = 0;; n++) {
                const uint32_t v1 = ld_relaxed(fp);
                const uint32_t ready = __ballot_sync(0xffffffffu, (int)(v0 - target) >= 0);
                v0 = v1;
                if (next < NKV && ((ready >> next) & 1)) {
                    flag_acquired();
                    do {
                        if (lane == 0) {
                            mbar_expect(bar + B_KVF + 8 * next, KV_SLOT);
                            bulk_g2s(sb + OFF_KV + next * KV_SLOT, g_kv + ((next + s0) & 15) * KV_SLOT, KV_SLOT, bar + B_KVF + 8 * next);
                        }
                        next++;
                    } while (next < NKV && ((ready >> next) & 1));
                }
                if (ready == 0xffffffffu) break;
                if ((n & 15) == 15 && __any_sync(0xffffffffu, give_up(bar + B_ABORT, n, 1 << 22))) break;
            }
            if (lane == 0) {
                flag_acquired();
                mbar_expect(bar + B_ST, 4096);
                bulk_g2s(sb + OFF_OS, g_stats, 4096, bar + B_ST);
                if (blockIdx.x == 0) g_sync[SY_EPOCH] = epoch + 1;
            }
            __syncwarp();
        }
    }
}

__device__ __forceinline__ void gemm_role(const uint32_t sb, __nv_bfloat16* __restrict__ out, const __nv_bfloat16* __restrict__ x, const int warp, const int lane, const int ti, const int tj) {
    const uint32_t bar = sb + OFF_BAR;
    const int tid = warp * 32 + lane, g = lane >> 2, c = lane & 3;
    const uint64_t dxn = mkdesc(sb + OFF_XN, 16, 1024, 1);
    uint32_t gi = 0;
    {
        float acc[32];
        pin(acc);
#pragma unroll 1
        for (int s = 0; s < 4; s++, gi++) {
            mbar_wait<NS_GC>(bar + B_GF + 8 * (gi & 3), (gi >> 2) & 1);
            const uint64_t db = mkdesc(sb + OFF_G + (gi & 3) * G_SLOT, 16, 1024, 1);
            wg_fence();
#pragma unroll
            for (int ks = 0; ks < 8; ks++) wg_ss(acc, dxn + (uint64_t)((s * 2 + (ks >> 2)) * 512 + (ks & 3) * 2), db + (uint64_t)(ks * 128), ks > 0 || s > 0);
            wg_commit();
            wg_wait<1>();
            if (s > 0 && lane == 0) mbar_arrive(bar + B_GE + 8 * ((gi - 1) & 3));
        }
        wg_wait<0>();
        pin(acc);
        if (lane == 0) mbar_arrive(bar + B_GE + 8 * ((gi - 1) & 3));
        constexpr float QS = 0.25f * 1.4426950408889634f;
        float kp, vfloor;
        load_stats(sb, lane, kp, vfloor);
        if (tid == 0) asm volatile("st.shared.v2.f32 [%0], {%1, %2};" ::"r"(bar + B_STAT), "f"(kp), "f"(vfloor) : "memory");
#pragma unroll
        for (int t = 0; t < 4; t++) {
            uint32_t v[4];
#pragma unroll
            for (int i = 0; i < 4; i++) v[i] = pack2(acc[8 * t + 2 * i] * QS, acc[8 * t + 2 * i + 1] * QS);
            sts128(sb + OFF_Q2 + t * 2048 + tid * 16, make_uint4(v[0], v[1], v[2], v[3]));
            float n0, n1;
            row_norm(v, n0, n1);
            const float n = (c & 1) ? n1 : n0;
            if (c < 2) asm volatile("st.shared.v2.f32 [%0], {%1, %2};" ::"r"(sb + OFF_QM + (t * 64 + warp * 16 + g + 8 * c) * 8), "f"(row_shift(n, kp)), "f"(n) : "memory");
        }
        __syncwarp();
        if (lane == 0) mbar_arrive(bar + B_Q2);
    }
#pragma unroll 1
    for (int p = 0; p < 2; p++) ffn1_pass<160>(sb, dxn, gi, p, warp, lane);
    ffn1_pass<128>(sb, dxn, gi, 2, warp, lane);
    float acc[64];
    {
        const uint32_t* xp = (const uint32_t*)(x + (size_t)(ti * 64 + warp * 16 + g) * D_MODEL + tj * 128) + c;
#pragma unroll
        for (int jb = 0; jb < 16; jb++) {
            const uint32_t a = __ldg(xp + jb * 4), b = __ldg(xp + jb * 4 + 8 * (D_MODEL / 2));
            acc[4 * jb] = bf_lo(a); acc[4 * jb + 1] = bf_hi(a); acc[4 * jb + 2] = bf_lo(b); acc[4 * jb + 3] = bf_hi(b);
        }
        pin(acc);
    }
#pragma unroll 1
    for (int kc = 0; kc < 32; kc++, gi++) {
        mbar_wait<NS_GC>(bar + B_GF + 8 * (gi & 3), (gi >> 2) & 1);
        const uint32_t sl = sb + OFF_G + (gi & 3) * G_SLOT;
        const uint64_t da = mkdesc(sl, 16, 512, 2), db = mkdesc(sl + 8192, 8192, 1024, 1);
        wg_fence();
#pragma unroll
        for (int ks = 0; ks < 4; ks++) wg_ss(acc, da + (uint64_t)((ks >> 1) * 256 + (ks & 1) * 2), db + (uint64_t)(ks * 128));
        wg_commit();
        wg_wait<1>();
        if (kc > 0 && lane == 0) mbar_arrive(bar + B_GE + 8 * ((gi - 1) & 3));
    }
    wg_wait<0>();
    if (lane == 0) mbar_arrive(bar + B_GE + 8 * 3);
    const int r = ((lane >> 3) & 1) * 8 + (lane & 7), uh = lane >> 4;
    uint32_t wa[8], ra[4];
#pragma unroll
    for (int i = 0; i < 8; i++) wa[i] = sb + OFF_XN + warp * 4096 + r * 256 + (((2 * i + uh) ^ (r & 7)) << 4);
#pragma unroll
    for (int i = 0; i < 4; i++) ra[i] = sb + OFF_XN + warp * 4096 + (2 * i + uh) * 256 + (((lane & 15) ^ ((2 * i + uh) & 7)) << 4);
    uint4* dst = (uint4*)(out + (size_t)(ti * 64 + warp * 16 + uh) * D_MODEL + tj * 128) + (lane & 15);
    pin(wa); pin(ra);
    asm volatile("" : "+l"(dst));
    mbar_wait<300>(bar + B_NEAR, 0);
#pragma unroll
    for (int n = 0; n < 4; n++) {
        mbar_wait(bar + B_GF + 8 * n, 1);
        if (n == 0) mbar_wait(bar + B_OR + 8, 0);
        const uint32_t sl = sb + OFF_G + n * G_SLOT;
        const uint64_t da = mkdesc(n == 0 ? sb + OFF_OS : sl, 16, 512, 2), db = mkdesc(sl + 8192, 8192, 1024, 1);
        wg_fence();
#pragma unroll
        for (int ks = 0; ks < 4; ks++) wg_ss(acc, da + (uint64_t)((ks >> 1) * 256 + (ks & 1) * 2), db + (uint64_t)(ks * 128));
        wg_commit();
    }
    wg_wait<0>();
    pin(acc);
    {
#pragma unroll
        for (int jb = 0; jb < 16; jb += 2)
            stsm4(wa[jb >> 1], pack2(acc[4 * jb], acc[4 * jb + 1]), pack2(acc[4 * jb + 2], acc[4 * jb + 3]),
                  pack2(acc[4 * jb + 4], acc[4 * jb + 5]), pack2(acc[4 * jb + 6], acc[4 * jb + 7]));
        __syncwarp();
#pragma unroll
        for (int i = 0; i < 8; i++) dst[i * 2 * (D_MODEL / 8)] = lds128(ra[i & 3] + (i >> 2) * 2048);
    }
}

__device__ __forceinline__ void producer_role(const uint32_t sb, const Maps& maps, const int warp, const int lane, const int ti, const int tj) {
    const uint32_t bar = sb + OFF_BAR;
    unsigned epoch;
    asm volatile("ld.shared.u32 %0, [%1];" : "=r"(epoch) : "r"(bar + B_EPOCH));
    if (warp == 0) {
        if (lane == 0) {
#pragma unroll 1
            for (uint32_t it = NKV; it < 32; it++) {
                const uint32_t s = it & (NKV - 1);
                mbar_wait<NS_KV>(bar + B_KVE + 8 * s, ((it / NKV) - (s == NKV - 1 ? 0 : 1)) & 1);
                mbar_expect(bar + B_KVF + 8 * s, KV_SLOT);
                bulk_g2s(sb + OFF_KV + s * KV_SLOT, g_kv + ((it + (ti >> 1)) & 15) * KV_SLOT, KV_SLOT, bar + B_KVF + 8 * s);
            }
            mbar_wait<NS_KV>(bar + B_KVE + 8 * (29 & (NKV - 1)), (29 / NKV) & 1);
            mbar_arrive(bar + B_NEAR);
        }
    } else if (lane != 0) {
    } else if (warp == 1) {
        mbar_wait<100>(bar + B_PRO, 0);
        mbar_wait<100>(bar + B_ST, 0);
#pragma unroll 1
        for (uint32_t gi = 0; gi < 64; gi++) {
            const uint32_t s = gi & 3, fb = bar + B_GF + 8 * s, dst = sb + OFF_G + s * G_SLOT;
            if (gi >= 4) mbar_wait<NS_GP>(bar + B_GE + 8 * s, ((gi >> 2) - 1) & 1);
            if (gi < 4) {
                mbar_expect(fb, 16384);
                tma2(dst, &maps.wq64, tj * 128 + 64, gi * 128, fb);
            } else if (gi < 28) {
                const int n = gi - 4;
                mbar_expect(fb, n < 16 ? 20480 : 16384);
                tma3(dst, n < 16 ? &maps.w1a : &maps.w1b, 0, (n & 7) * 64, tj * 14 + (n >> 3) * 5, fb);
            } else if (gi < 56) {
                const int n = gi - 28;
                int kc = n + tj * 7; if (kc >= 28) kc -= 28;
                mbar_expect(fb, 24576);
                tma3(dst + 8192, &maps.w2, 0, kc * 64, tj * 2, fb);
                if (n == 0) flag_wait(&g_sync[SY_H + ti * 32], (epoch + 1) * 12u, 200, bar);
                bulk_g2s(dst, g_h + (size_t)(ti * 56 + kc * 2) * 4096, 8192, fb);
            } else {
                const int n = gi - 56, rnd = n >> 2, jj = (n + tj) & 3;
                mbar_expect(fb, n == 4 ? 16384 : 24576);
                tma3(dst + 8192, &maps.wo, 0, jj * 128 + rnd * 64, tj * 2, fb);
                if (n == 0) flag_wait(&g_sync[SY_O + (ti * 2) * 32], (epoch + 1) * 4u, 300, bar);
                if (rnd == 0) bulk_g2s(dst, g_o + (size_t)(ti * 16 + jj * 4) * 4096, 8192, fb);
            }
        }
        mbar_wait<300>(bar + B_NEAR, 0);
        flag_wait_fast(&g_sync[SY_O + (ti * 2 + 1) * 32], (epoch + 1) * 32u, bar);
#pragma unroll 1
        for (uint32_t n = 1; n < 4; n++)
            bulk_g2s(sb + OFF_G + n * G_SLOT, g_o + (size_t)(ti * 16 + ((n + tj) & 3) * 4 + 2) * 4096, 8192, bar + B_GF + 8 * n);
    } else if (warp == 2) {
#pragma unroll 1
        for (int p = 0; p < 3; p++) {
            mbar_wait<200>(bar + B_HR + 8 * p, 0);
            bulk_s2g(g_h + (size_t)(ti * 56 + tj * 14 + p * 5) * 4096, sb + OFF_G + 3 * G_SLOT, p < 2 ? 20480 : 16384);
            bulk_commit();
            bulk_wait_read();
            mbar_arrive_n(bar + B_GE + 8 * 3, 4);
            bulk_wait();
            flag_add(&g_sync[SY_H + ti * 32]);
        }
    } else {
        mbar_wait<300>(bar + B_OR, 0);
        bulk_s2g(g_o + (size_t)(ti * 16 + tj * 4) * 4096, sb + OFF_OS, 8192);
        bulk_commit();
        bulk_wait();
        mbar_arrive(bar + B_OE);
        flag_add(&g_sync[SY_O + (ti * 2) * 32]);
    }
}

template <int NR>
__device__ __forceinline__ void layer_norm_rows(const uint4 (&u)[NR][2], const int (&row)[NR], const uint32_t sb, const int lane) {
    float v[NR][16], s[NR], ss[NR];
#pragma unroll
    for (int rr = 0; rr < NR; rr++) {
        const float x0 = bf_lo(__shfl_sync(0xffffffffu, u[rr][0].x, 0));
#pragma unroll
        for (int h = 0; h < 2; h++) {
            v[rr][8 * h + 0] = bf_lo(u[rr][h].x) - x0; v[rr][8 * h + 1] = bf_hi(u[rr][h].x) - x0; v[rr][8 * h + 2] = bf_lo(u[rr][h].y) - x0; v[rr][8 * h + 3] = bf_hi(u[rr][h].y) - x0;
            v[rr][8 * h + 4] = bf_lo(u[rr][h].z) - x0; v[rr][8 * h + 5] = bf_hi(u[rr][h].z) - x0; v[rr][8 * h + 6] = bf_lo(u[rr][h].w) - x0; v[rr][8 * h + 7] = bf_hi(u[rr][h].w) - x0;
        }
        float a0 = 0.f, a1 = 0.f, b0 = 0.f, b1 = 0.f;
#pragma unroll
        for (int i = 0; i < 16; i += 2) { a0 += v[rr][i]; a1 += v[rr][i + 1]; b0 = fmaf(v[rr][i], v[rr][i], b0); b1 = fmaf(v[rr][i + 1], v[rr][i + 1], b1); }
        s[rr] = a0 + a1; ss[rr] = b0 + b1;
    }
#pragma unroll
    for (int d = 16; d; d >>= 1)
#pragma unroll
        for (int rr = 0; rr < NR; rr++) { s[rr] += __shfl_xor_sync(0xffffffffu, s[rr], d); ss[rr] += __shfl_xor_sync(0xffffffffu, ss[rr], d); }
#pragma unroll
    for (int rr = 0; rr < NR; rr++) {
        const float m = s[rr] * (1.0f / 512.0f);
        const float rs = rsqrtf(fmaxf(fmaf(-m, m, ss[rr] * (1.0f / 512.0f)), 0.f) + 1e-5f), c = -m * rs;
#pragma unroll
        for (int h = 0; h < 2; h++) {
            uint4 o;
            o.x = pack2(fmaf(v[rr][8 * h + 0], rs, c), fmaf(v[rr][8 * h + 1], rs, c)); o.y = pack2(fmaf(v[rr][8 * h + 2], rs, c), fmaf(v[rr][8 * h + 3], rs, c));
            o.z = pack2(fmaf(v[rr][8 * h + 4], rs, c), fmaf(v[rr][8 * h + 5], rs, c)); o.w = pack2(fmaf(v[rr][8 * h + 6], rs, c), fmaf(v[rr][8 * h + 7], rs, c));
            sts128(sb + OFF_XN + ((lane >> 3) + 4 * h) * 8192 + row[rr] * 128 + (((lane & 7) ^ (row[rr] & 7)) << 4), o);
        }
    }
}

__global__ void __launch_bounds__(512, 1)
fused_kernel(const __nv_bfloat16* __restrict__ x, const __nv_bfloat16* __restrict__ wk, const __nv_bfloat16* __restrict__ wv,
             __nv_bfloat16* __restrict__ out, const __grid_constant__ Maps maps) {
    extern __shared__ uint8_t smem_raw[];
    const uint32_t sb = ((uint32_t)__cvta_generic_to_shared(smem_raw) + 1023u) & ~1023u;
    const uint32_t bar = sb + OFF_BAR;
    const int wid = __shfl_sync(0xffffffffu, threadIdx.x >> 5, 0), wg = wid >> 2, warp = wid & 3, lane = threadIdx.x & 31;
    const int ti = blockIdx.x >> 2, tj = blockIdx.x & 3;
    const int rowA = tj * 16 + (threadIdx.x >> 5);
    const uint4* xp = (const uint4*)(x + (size_t)ti * 64 * D_MODEL) + lane;
    uint4 xa[1][2];
#pragma unroll
    for (int h = 0; h < 2; h++) xa[0][h] = ldx(xp + rowA * 64 + h * 32);
    unsigned epoch = 0;
    if (threadIdx.x == 416) {
        mbar_init(bar + B_WKV, 1);
        fence_async_smem();
        mbar_expect(bar + B_WKV, 32768);
        bulk_g2s(sb + OFF_WKV, wk, 16384, bar + B_WKV);
        bulk_g2s(sb + OFF_WKV + 16384, wv, 16384, bar + B_WKV);
    }
    if (threadIdx.x == 448) {
        asm volatile("ld.relaxed.gpu.global.u32 %0, [%1];" : "=r"(epoch) : "l"(&g_sync[SY_EPOCH]) : "memory");
        mbar_init(bar + B_WQ1, 1); mbar_init(bar + B_ST, 1); mbar_init(bar + B_OE, 1); mbar_init(bar + B_NEAR, 1); mbar_init(bar + B_PRO, 12); mbar_init(bar + B_Q2, 4);
        mbar_init(bar + B_HR, 4); mbar_init(bar + B_HR + 8, 4); mbar_init(bar + B_HR + 16, 4); mbar_init(bar + B_OR, 8); mbar_init(bar + B_OR + 8, 8);
#pragma unroll
        for (int i = 0; i < 4; i++) { mbar_init(bar + B_KVF + 8 * i, 1); mbar_init(bar + B_KVE + 8 * i, 8); mbar_init(bar + B_GF + 8 * i, 1); mbar_init(bar + B_GE + 8 * i, 4); }
    }
    {
        const int r[1] = {rowA};
        layer_norm_rows<1>(xa, r, sb, lane);
    }
    if (threadIdx.x == 448) { asm volatile("st.shared.v2.u32 [%0], {%1, 0};" ::"r"(bar + B_EPOCH), "r"(epoch) : "memory"); }
    fence_async_smem();
    if (wg == 2) {
        bar_sync(3, 512);
        asm volatile("setmaxnreg.dec.sync.aligned.u32 %0;" ::"n"(R_GEM));
        kv_projection(sb, warp, lane, ti, tj);
        gemm_role(sb, out, x, warp, lane, ti, tj);
    } else {
        bar_arrive(3, 512);
        const int slotB = (wg == 3 ? 8 + warp : wid) * 4;
        int r[4];
        uint4 xb[4][2];
#pragma unroll
        for (int rr = 0; rr < 4; rr++) {
            r[rr] = slotB + rr + (slotB + rr >= tj * 16 ? 16 : 0);
#pragma unroll
            for (int h = 0; h < 2; h++) xb[rr][h] = ldx(xp + r[rr] * 64 + h * 32);
        }
        if (wid == 15) {
#pragma unroll
            for (int m = 0; m < 4; m++) {
                const int u = m * 32 + lane, n = (u >> 4) * 8 + (u & 7);
                const bool poly = !(n & 1) && ((PM_POLY >> (8 * (n >> 4) + 4 * ((n >> 3) & 1))) & 1);
                sts128(sb + OFF_AUG + u * 16, make_uint4((u & 8) ? 0u : (poly ? pack2(0x1p-22f, 125.f * 0x1p-22f) : 0x3F80u), 0u, 0u, 0u));
            }
        }
        if (threadIdx.x == 448) {
            fence_async_smem();
            mbar_expect(bar + B_WQ1, 65536);
#pragma unroll
            for (int h = 0; h < 4; h++) tma2(sb + OFF_WQ1 + h * 16384, &maps.wq64, tj * 128, h * 128, bar + B_WQ1);
        }
        bar_sync(5, 512);
        layer_norm_rows<4>(xb, r, sb, lane);
        fence_async_smem();
        if (wg == 3) {
            bar_arrive(1, 384);
            bar_sync(4, 128);
            asm volatile("setmaxnreg.dec.sync.aligned.u32 %0;" ::"n"(R_PRO));
            producer_role(sb, maps, warp, lane, ti, tj);
        } else {
            asm volatile("setmaxnreg.inc.sync.aligned.u32 %0;" ::"n"(R_ATT));
            attention_role(sb, wg, warp, lane, ti, tj);
        }
    }
}

typedef CUresult (*EncodeFn)(CUtensorMap*, CUtensorMapDataType, cuuint32_t, void*, const cuuint64_t*, const cuuint64_t*, const cuuint32_t*, const cuuint32_t*,
                             CUtensorMapInterleave, CUtensorMapSwizzle, CUtensorMapL2promotion, CUtensorMapFloatOOBfill);

void encode(EncodeFn fn, CUtensorMap* m, const void* p, int rank, const cuuint64_t* dims, const cuuint64_t* strides, const cuuint32_t* box, CUtensorMapSwizzle sw) {
    const cuuint32_t es[3] = {1, 1, 1};
    fn(m, CU_TENSOR_MAP_DATA_TYPE_BFLOAT16, rank, const_cast<void*>(p), dims, strides, box, es, CU_TENSOR_MAP_INTERLEAVE_NONE, sw,
       CU_TENSOR_MAP_L2_PROMOTION_L2_128B, CU_TENSOR_MAP_FLOAT_OOB_FILL_NONE);
}

}

extern "C" void kernel_launch(void* const* d_in, const int* in_sizes, int n_in, void* d_out, int out_size) {
    (void)in_sizes; (void)n_in; (void)out_size;
    const void *x = d_in[0], *wq = d_in[1], *wk = d_in[2], *wv = d_in[3], *wo = d_in[4], *w1 = d_in[6], *w2 = d_in[7];
    static EncodeFn fn = nullptr;
    if (!fn) {
        void* f = nullptr;
        cudaDriverEntryPointQueryResult qr;
        cudaGetDriverEntryPoint("cuTensorMapEncodeTiled", &f, cudaEnableDefault, &qr);
        fn = (EncodeFn)f;
        cudaFuncSetAttribute(fused_kernel, cudaFuncAttributeMaxDynamicSharedMemorySize, SMEM_BYTES);
    }
    Maps m;
    {
        const cuuint64_t d[2] = {512, 512}, s[1] = {1024};
        const cuuint32_t b64[2] = {64, 128};
        encode(fn, &m.wq64, wq, 2, d, s, b64, CU_TENSOR_MAP_SWIZZLE_128B);
    }
    {
        const cuuint64_t d[3] = {32, 512, 56}, s[2] = {D_FF * 2, 64};
        const cuuint32_t ba[3] = {32, 64, 5}, bb[3] = {32, 64, 4};
        encode(fn, &m.w1a, w1, 3, d, s, ba, CU_TENSOR_MAP_SWIZZLE_64B);
        encode(fn, &m.w1b, w1, 3, d, s, bb, CU_TENSOR_MAP_SWIZZLE_64B);
    }
    {
        const cuuint64_t d2[3] = {64, D_FF, 8}, dO[3] = {64, 512, 8}, s[2] = {1024, 128};
        const cuuint32_t b[3] = {64, 64, 2};
        encode(fn, &m.w2, w2, 3, d2, s, b, CU_TENSOR_MAP_SWIZZLE_128B);
        encode(fn, &m.wo, wo, 3, dO, s, b, CU_TENSOR_MAP_SWIZZLE_128B);
    }
    fused_kernel<<<128, 512, SMEM_BYTES>>>((const __nv_bfloat16*)x, (const __nv_bfloat16*)wk, (const __nv_bfloat16*)wv, (__nv_bfloat16*)d_out, m);
}
```
